```python
import torch

def _softmax(x, axis=-1):
    return torch.softmax(x, dim=axis)
def _gelu(x):
    return torch.nn.functional.gelu(x, approximate="tanh")
def _silu(x):
    return torch.nn.functional.silu(x)
def _sigmoid(x):
    return torch.sigmoid(x)
def _layernorm(x, axis=-1, eps=1e-5):
    m = x.mean(dim=axis, keepdim=True)
    v = x.var(dim=axis, keepdim=True, unbiased=False)
    return (x - m) / torch.sqrt(v + eps)
def _scatter_add(tgt, idx, src, axis=0):
    return tgt.clone().index_add_(axis, idx, src)
def _segment_sum(src, seg, n):
    out = torch.zeros((n,) + src.shape[1:], dtype=src.dtype)
    return out.index_add_(0, seg, src)
def _pad(x, pw):
    flat = tuple(v for pair in reversed(pw) for v in pair)
    return torch.nn.functional.pad(x, flat)

kernel_name = 'parallel_sum__compressed_kv_cla__dense_activation_relu__prompt'

def setup_inputs():

    _w = (lambda a: (lambda t: t.to(torch.bfloat16) if t.is_floating_point() else t)(torch.as_tensor(a)))
    def _A_setup():
        B, H, Sq, Sk, D, M = 1, 32, 2048, 2048, 128, 512
        Dc = 4 * D
        return {
            "x": _w((lambda *s: torch.randn(*s, dtype=torch.bfloat16) * 0.05)(B, Sq, M)),
            "c_kv": _w((lambda *s: torch.randn(*s, dtype=torch.bfloat16) * 1.6)(B, Sk, Dc)),
            "w_q": _w((lambda *s: torch.randn(*s, dtype=torch.bfloat16) * 0.8)(M, H, D) * (M ** -0.5)),
            "w_uk": _w((lambda *s: torch.randn(*s, dtype=torch.bfloat16) * 0.8)(Dc, H, D) * (Dc ** -0.5)),
            "w_uv": _w((lambda *s: torch.randn(*s, dtype=torch.bfloat16) * 1.6)(Dc, H, D) * (Dc ** -0.5)),
            "w_o": _w((lambda *s: torch.randn(*s, dtype=torch.bfloat16) * 1.6)(H, D, M) * ((H * D) ** -0.5)),
        }
    _A_in = _A_setup()

    def _B_setup():
        B, S, D, Dff = 1, 2048, 512, 1792
        return {
            "x": _w((lambda *s: torch.randn(*s, dtype=torch.bfloat16) * 0.05)(B, S, D)),
            "w1": _w((lambda *s: torch.randn(*s, dtype=torch.bfloat16) * 0.05)(D, Dff)),
            "w2": _w((lambda *s: torch.randn(*s, dtype=torch.bfloat16) * 0.05)(Dff, D)),
        }
    _B_in = _B_setup()

    return {
        "A_x": _A_in["x"],
        "A_c_kv": _A_in["c_kv"],
        "A_w_q": _A_in["w_q"],
        "A_w_uk": _A_in["w_uk"],
        "A_w_uv": _A_in["w_uv"],
        "A_w_o": _A_in["w_o"],
        "B_x": _B_in["x"],
        "B_w1": _B_in["w1"],
        "B_w2": _B_in["w2"],
    }

def reference(A_x, A_c_kv, A_w_q, A_w_uk, A_w_uv, A_w_o, B_x, B_w1, B_w2):
    def _A_ref(x, c_kv, w_q, w_uk, w_uv, w_o):
        B, Sq, M = x.shape[0], x.shape[1], x.shape[2]
        Sk = c_kv.shape[1]
        H, D = w_q.shape[1], w_q.shape[2]
        q = torch.einsum("bqm,mhd->bhqd", x, w_q)
        k = torch.einsum("bkc,chd->bhkd", c_kv, w_uk)
        v = torch.einsum("bkc,chd->bhkd", c_kv, w_uv)
        scores = torch.einsum("bhqd,bhkd->bhqk", q, k) * (D ** -0.5)
        off = Sk - Sq
        qi = torch.arange(Sq)[:, None]
        kj = torch.arange(Sk)[None, :]
        cmask = kj <= (qi + off)
        scores = torch.where(cmask[None, None], scores, -1e9)
        p = _softmax(scores, axis=-1)
        ctx = torch.einsum("bhqk,bhkd->bhqd", p, v)
        return torch.einsum("bhqd,hdm->bqm", ctx, w_o)

    def _B_ref(x, w1, w2):
        h = torch.einsum("bsd,df->bsf", x, w1)
        zero = torch.zeros_like(h)
        h = torch.maximum(h, zero)
        return torch.einsum("bsf,fd->bsd", h, w2)

    x = A_x
    xn = _layernorm(x, axis=-1)
    return x + _A_ref(xn, A_c_kv, A_w_q, A_w_uk, A_w_uv, A_w_o) + _B_ref(xn, B_w1, B_w2)
```

```cpp
#include <cuda_runtime.h>
#include <cuda_bf16.h>
#include <cuda.h>
#include <stdint.h>
#include <string.h>

namespace {

constexpr int SEQ = 2048, DM = 512, NH = 32, DFF = 1792;
constexpr int NSLOT = 7;
constexpr int SLOT = 32768;
constexpr int BLK = 16384;
constexpr int NPAIR = 66;
constexpr int NCTA = 2 * NPAIR;
constexpr int MAX_LIST = 416;
constexpr int MAX_ITEMS = 128;
static_assert(MAX_ITEMS == 128, "item buffer is cleared by one warp");
constexpr int NCHUNK = NH + DFF / 128;
constexpr int SMEM_BYTES = NSLOT * SLOT + 1024 + 256 + 4 * MAX_ITEMS;

enum { IT_NONE = 0, IT_PROJ = 1, IT_ATTN = 2, IT_OUT = 3, IT_END = 4 };

constexpr int FL_XN = 0;
constexpr int FL_KV = 1;
constexpr int FL_ACT = FL_KV + 32;
constexpr int FL_COUNT = FL_ACT + 8 * 6;
constexpr int FL_STRIDE = 8;

struct Params {
  CUtensorMap tm_ckv, tm_wq, tm_wuk, tm_wuv, tm_w1, tm_wo, tm_w2, tm_out;
  const __nv_bfloat16* x;
  __nv_bfloat16* out;
  uint32_t pf_bytes[8];
  uint32_t n_items;
  uint32_t list[MAX_LIST];
  uint8_t order[8][48];
  uint8_t pos[8][48];
  uint8_t tile[160];
};

__device__ __align__(1024) uint8_t g_xn[4 * 32 * BLK];
__device__ __align__(1024) uint8_t g_K[NH * 32 * BLK];
__device__ __align__(1024) uint8_t g_V[NH * 32 * BLK];
__device__ __align__(1024) uint8_t g_act[NCHUNK * 32 * BLK];
__device__ uint32_t g_flags[FL_COUNT * FL_STRIDE];
__device__ uint32_t g_epoch[NCTA];
__device__ uint32_t g_queue;
#define TRACE_ITEM
#define T5(n)
#define TR3(cond, n)

__device__ __forceinline__ uint32_t smem_u32(const void* p) { return (uint32_t)__cvta_generic_to_shared(p); }
__device__ __forceinline__ void mbar_init(uint32_t bar, uint32_t cnt) {
  asm volatile("mbarrier.init.shared::cta.b64 [%0], %1;" ::"r"(bar), "r"(cnt) : "memory");
}
__device__ __forceinline__ void mbar_expect_tx(uint32_t bar, uint32_t bytes) {
  asm volatile("mbarrier.arrive.expect_tx.shared::cta.b64 _, [%0], %1;" ::"r"(bar), "r"(bytes) : "memory");
}
__device__ __forceinline__ uint32_t mapa(uint32_t addr, uint32_t rank) {
  uint32_t r;
  asm volatile("mapa.shared::cluster.u32 %0, %1, %2;" : "=r"(r) : "r"(addr), "r"(rank));
  return r;
}
__device__ __forceinline__ bool mbar_try_wait(uint32_t bar, uint32_t parity) {
  uint32_t ok;
  asm volatile(
      "{\n .reg .pred p;\n mbarrier.try_wait.parity.shared::cta.b64 p, [%1], %2;\n selp.u32 %0, 1, 0, p;\n}"
      : "=r"(ok)
      : "r"(bar), "r"(parity)
      : "memory");
  return ok;
}
__device__ __forceinline__ void mbar_wait(uint32_t bar, uint32_t parity) {
  while (!mbar_try_wait(bar, parity)) {
  }
}
__device__ __forceinline__ void mbar_wait_bounded(uint32_t bar, uint32_t parity) {
  asm volatile(
      "{\n .reg .pred p;\n .reg .u32 n;\n mov.u32 n, 0;\n BOUNDED_LOOP:\n add.u32 n, n, 1;\n setp.gt.u32 p, n, 0x1000000;\n @p trap;\n"
      " mbarrier.try_wait.parity.shared::cta.b64 p, [%0], %1;\n @!p bra.uni BOUNDED_LOOP;\n}" ::"r"(bar),
      "r"(parity)
      : "memory");
}
__device__ __forceinline__ bool mbar_test(uint32_t bar, uint32_t parity) {
  uint32_t ok;
  asm volatile(
      "{\n .reg .pred p;\n mbarrier.test_wait.parity.shared::cta.b64 p, [%1], %2;\n selp.u32 %0, 1, 0, p;\n}"
      : "=r"(ok)
      : "r"(bar), "r"(parity)
      : "memory");
  return ok;
}
__device__ __forceinline__ void mbar_wait_uni(uint32_t bar, uint32_t parity) {
  asm volatile(
      "{\n .reg .pred p;\n WAIT_LOOP:\n mbarrier.try_wait.parity.shared::cta.b64 p, [%0], %1;\n @!p bra.uni WAIT_LOOP;\n}" ::"r"(bar),
      "r"(parity)
      : "memory");
}
__device__ __forceinline__ void mbar_wait_uni_unless(uint32_t ok, uint32_t bar, uint32_t parity) {
  asm volatile(
      "{\n .reg .pred p;\n setp.ne.u32 p, %2, 0;\n @p bra.uni WAIT_DONE;\n WAIT_LOOP:\n"
      " mbarrier.try_wait.parity.shared::cta.b64 p, [%0], %1;\n @!p bra.uni WAIT_LOOP;\n WAIT_DONE:\n}" ::"r"(bar),
      "r"(parity), "r"(ok)
      : "memory");
}
__device__ __forceinline__ void mbar_arrive_local(uint32_t bar) {
  asm volatile("mbarrier.arrive.shared::cta.b64 _, [%0];" ::"r"(bar) : "memory");
}
__device__ __forceinline__ unsigned long long globaltimer() {
  unsigned long long t;
  asm volatile("mov.u64 %0, %%globaltimer;" : "=l"(t));
  return t;
}
__device__ __forceinline__ void bulk_g2s(uint32_t dst, const void* src, uint32_t bytes, uint32_t bar) {
  asm volatile("cp.async.bulk.shared::cluster.global.mbarrier::complete_tx::bytes [%0], [%1], %2, [%3];" ::"r"(dst),
               "l"(src), "r"(bytes), "r"(bar)
               : "memory");
}
__device__ __forceinline__ void bulk_g2s_mc(uint32_t dst, const void* src, uint32_t bytes, uint32_t bar) {
  asm volatile(
      "cp.async.bulk.shared::cluster.global.mbarrier::complete_tx::bytes.multicast::cluster [%0], [%1], %2, [%3], %4;" ::"r"(dst),
      "l"(src), "r"(bytes), "r"(bar), "h"((uint16_t)3)
      : "memory");
}
__device__ __forceinline__ void tma_2d(uint32_t dst, const CUtensorMap* m, int c0, int c1, uint32_t bar) {
  asm volatile("cp.async.bulk.tensor.2d.shared::cluster.global.mbarrier::complete_tx::bytes [%0], [%1, {%3, %4}], [%2];" ::"r"(dst),
               "l"(m), "r"(bar), "r"(c0), "r"(c1)
               : "memory");
}
__device__ __forceinline__ void tma_2d_mc(uint32_t dst, const CUtensorMap* m, int c0, int c1, uint32_t bar) {
  asm volatile(
      "cp.async.bulk.tensor.2d.shared::cluster.global.mbarrier::complete_tx::bytes.multicast::cluster [%0], [%1, {%3, %4}], [%2], %5;" ::"r"(dst),
      "l"(m), "r"(bar), "r"(c0), "r"(c1), "h"((uint16_t)3)
      : "memory");
}
__device__ __forceinline__ void tma_prefetch(const CUtensorMap* m, int c0, int c1) {
  asm volatile("cp.async.bulk.prefetch.tensor.2d.L2.global.tile [%0, {%1, %2}];" ::"l"(m), "r"(c0), "r"(c1) : "memory");
}
__device__ __forceinline__ void cluster_arrive() { asm volatile("barrier.cluster.arrive.relaxed.aligned;" ::: "memory"); }
__device__ __forceinline__ void cluster_wait() { asm volatile("barrier.cluster.wait.aligned;" ::: "memory"); }
__device__ __forceinline__ void wg_fence() { asm volatile("wgmma.fence.sync.aligned;" ::: "memory"); }
__device__ __forceinline__ void wg_commit() { asm volatile("wgmma.commit_group.sync.aligned;" ::: "memory"); }
template <int N>
__device__ __forceinline__ void wg_wait() {
  asm volatile("wgmma.wait_group.sync.aligned %0;" ::"n"(N) : "memory");
}
__device__ __forceinline__ void fence_regs(float (&a)[64]) {
#pragma unroll
  for (int i = 0; i < 64; i++) asm volatile("" : "+f"(a[i])::"memory");
}
__device__ __forceinline__ void fence_regs(uint32_t (&a)[32]) {
#pragma unroll
  for (int i = 0; i < 32; i++) asm volatile("" : "+r"(a[i])::"memory");
}
__device__ __forceinline__ void fence_regs(float (&a)[4]) { asm volatile("" : "+f"(a[0]), "+f"(a[1]), "+f"(a[2]), "+f"(a[3])::"memory"); }
__device__ __forceinline__ uint32_t pack_bf16(float lo, float hi) {
  uint32_t r;
  asm("cvt.rn.bf16x2.f32 %0, %1, %2;" : "=r"(r) : "f"(hi), "f"(lo));
  return r;
}
__device__ __forceinline__ uint32_t pack_bf16_relu(float lo, float hi) {
  uint32_t r;
  asm("cvt.rn.relu.bf16x2.f32 %0, %1, %2;" : "=r"(r) : "f"(hi), "f"(lo));
  return r;
}
__device__ __forceinline__ float ex2(float x) {
  float y;
  asm("ex2.approx.ftz.f32 %0, %1;" : "=f"(y) : "f"(x));
  return y;
}
__device__ __forceinline__ float bf16_round(float x) { return __bfloat162float(__float2bfloat16_rn(x)); }
__device__ __forceinline__ float bf_lo(uint32_t v) { return __uint_as_float(v << 16); }
__device__ __forceinline__ float bf_hi(uint32_t v) { return __uint_as_float(v & 0xffff0000u); }

__device__ __forceinline__ uint32_t ld_acquire(const uint32_t* p) {
  uint32_t v;
  asm volatile("ld.acquire.gpu.global.u32 %0, [%1];" : "=r"(v) : "l"(p) : "memory");
  return v;
}

__device__ __forceinline__ uint32_t wait_item(uint32_t addr) {
  uint32_t v;
  asm volatile(
      "{\n .reg .pred p;\n ITEM_LOOP:\n ld.volatile.shared.u32 %0, [%1];\n setp.eq.u32 p, %0, 0;\n @p bra ITEM_LOOP;\n}"
      : "=r"(v)
      : "r"(addr)
      : "memory");
  return v;
}
#define ACC8(a, o) "+f"(a[o + 0]), "+f"(a[o + 1]), "+f"(a[o + 2]), "+f"(a[o + 3]), "+f"(a[o + 4]), "+f"(a[o + 5]), "+f"(a[o + 6]), "+f"(a[o + 7])
#define ACC32(a, o) ACC8(a, o), ACC8(a, o + 8), ACC8(a, o + 16), ACC8(a, o + 24)
#define ACC64(a) ACC32(a, 0), ACC32(a, 32)
#define R64                                                                                                   \
  "{%0,%1,%2,%3,%4,%5,%6,%7,%8,%9,%10,%11,%12,%13,%14,%15,%16,%17,%18,%19,%20,%21,%22,%23,%24,%25,%26,%27,%28," \
  "%29,%30,%31,%32,%33,%34,%35,%36,%37,%38,%39,%40,%41,%42,%43,%44,%45,%46,%47,%48,%49,%50,%51,%52,%53,%54,%55," \
  "%56,%57,%58,%59,%60,%61,%62,%63}"

template <int TB>
__device__ __forceinline__ void wgmma_ss(float (&d)[64], uint32_t alo, uint32_t ahi, uint32_t blo, uint32_t bhi, int scale_d) {
  asm volatile(
      "{\n .reg .pred p;\n .reg .b64 da, db;\n setp.ne.b32 p, %68, 0;\n mov.b64 da, {%64, %65};\n mov.b64 db, {%66, %67};\n"
      " wgmma.mma_async.sync.aligned.m64n128k16.f32.bf16.bf16 " R64 ", da, db, p, 1, 1, 0, %69;\n}"
      : ACC64(d)
      : "r"(alo), "r"(ahi), "r"(blo), "r"(bhi), "r"(scale_d), "n"(TB));
}
template <int TB>
__device__ __forceinline__ void wgmma_rs(float (&d)[64], uint32_t a0, uint32_t a1, uint32_t a2, uint32_t a3, uint32_t blo, uint32_t bhi,
                                         int scale_d) {
  asm volatile(
      "{\n .reg .pred p;\n .reg .b64 db;\n setp.ne.b32 p, %70, 0;\n mov.b64 db, {%68, %69};\n"
      " wgmma.mma_async.sync.aligned.m64n128k16.f32.bf16.bf16 " R64 ", {%64,%65,%66,%67}, db, p, 1, 1, %71;\n}"
      : ACC64(d)
      : "r"(a0), "r"(a1), "r"(a2), "r"(a3), "r"(blo), "r"(bhi), "r"(scale_d), "n"(TB));
}

template <int H>
__device__ __forceinline__ void wgmma_rs_n64(float (&d)[64], uint32_t a0, uint32_t a1, uint32_t a2, uint32_t a3, uint32_t blo, uint32_t bhi,
                                             int scale_d) {
  asm volatile(
      "{\n .reg .pred p;\n .reg .b64 db;\n setp.ne.b32 p, %38, 0;\n mov.b64 db, {%36, %37};\n"
      " wgmma.mma_async.sync.aligned.m64n64k16.f32.bf16.bf16 "
      "{%0,%1,%2,%3,%4,%5,%6,%7,%8,%9,%10,%11,%12,%13,%14,%15,%16,%17,%18,%19,%20,%21,%22,%23,%24,%25,%26,%27,%28,%29,%30,%31}"
      ", {%32,%33,%34,%35}, db, p, 1, 1, 0;\n}"
      : ACC32(d, 32 * H)
      : "r"(a0), "r"(a1), "r"(a2), "r"(a3), "r"(blo), "r"(bhi), "r"(scale_d));
}

constexpr uint32_t DESC_SW_HI = 64u | (1u << 30);
constexpr uint32_t DESC_SWK_LO = 1u << 16;
constexpr uint32_t DESC_SWN_LO = 1024u << 16;
constexpr uint32_t DESC_NSK_LO = 8u << 16;
constexpr uint32_t DESC_NSK_HI = 128u;
constexpr uint32_t DESC_NSN_LO = 128u << 16;
constexpr uint32_t DESC_NSN_HI = 8u;

struct Cons {
  uint32_t slot16;
  uint32_t full0;
  uint32_t rel0;
  uint32_t ph;
  uint32_t sigcnt;
  int ptr;
  int wg, warp, lane;
  bool releaser;
  uint32_t* pend;
  __device__ __forceinline__ void stamp(uint32_t) {}
  int pend_mode;
  __device__ __forceinline__ int next() {
    int s = ptr;
    ptr = (ptr == NSLOT - 1) ? 0 : ptr + 1;
    return s;
  }
  __device__ __forceinline__ void wait_full(int s) {
    mbar_wait_uni(full0 + 8 * s, (ph >> s) & 1);
    ph ^= 1u << s;
  }
  __device__ __forceinline__ bool probe(int s) { return mbar_test(full0 + 8 * s, (ph >> s) & 1); }
  __device__ __forceinline__ void finish(int s, bool ok) {
    mbar_wait_uni_unless(ok, full0 + 8 * s, (ph >> s) & 1);
    ph ^= 1u << s;
  }
  __device__ __forceinline__ void finish_all(uint32_t slots, bool ok) {
    asm volatile(
        "{\n .reg .pred p;\n .reg .b32 m, s, a, t;\n setp.ne.u32 p, %0, 0;\n @p bra.uni ALL_DONE;\n mov.b32 m, %1;\n"
        " ALL_LOOP:\n bfind.u32 s, m;\n shl.b32 a, s, 3;\n add.u32 a, a, %2;\n shr.u32 t, %3, s;\n and.b32 t, t, 1;\n"
        " mbarrier.try_wait.parity.shared::cta.b64 p, [a], t;\n shl.b32 t, 1, s;\n @p xor.b32 m, m, t;\n"
        " setp.ne.u32 p, m, 0;\n @p bra.uni ALL_LOOP;\n ALL_DONE:\n}" ::"r"((uint32_t)ok),
        "r"(slots), "r"(full0), "r"(ph)
        : "memory");
    ph ^= slots;
  }
  template <int N>
  __device__ __forceinline__ void mma_wait() {
    stamp(4 + N);
    wg_wait<N>();
    stamp(6 + N);
  }
  __device__ __forceinline__ void release(int s) {
    asm volatile("{\n .reg .pred p;\n setp.ne.b32 p, %1, 0;\n @p mbarrier.arrive.shared::cluster.b64 _, [%0];\n}" ::"r"(rel0 + 8 * s),
                 "r"((int)releaser)
                 : "memory");
  }
  __device__ __forceinline__ void release(int s, int count) {
    asm volatile("{\n .reg .pred p;\n setp.ne.b32 p, %2, 0;\n @p mbarrier.arrive.shared::cluster.b64 _, [%0], %1;\n}" ::"r"(rel0 + 8 * s),
                 "r"(count), "r"((int)releaser)
                 : "memory");
  }
  __device__ __forceinline__ uint32_t saddr(int s) const { return slot16 + s * (SLOT >> 4); }
  __device__ __forceinline__ uint32_t uaddr(int s) const { return saddr(s); }
  __device__ __forceinline__ void signal() {
    asm volatile("red.release.cta.shared::cta.add.u32 [%0], 1;" ::"r"(sigcnt) : "memory");
  }
  __device__ __forceinline__ void turn_begin() {
    stamp(1);
    asm volatile("bar.sync %0, 256;" ::"r"(1 + wg) : "memory");
    stamp(2);
  }
  __device__ __forceinline__ void turn_end() {
    asm volatile("bar.arrive %0, 256;" ::"r"(2 - wg) : "memory");
    stamp(3);
  }
  __device__ __forceinline__ void leave() {
    if (lane == 0) mbar_arrive_local(full0 + 136);
    __syncwarp();
    cluster_arrive();
  }
  __device__ __forceinline__ void set_pend(uint8_t* blk) {
    pend = reinterpret_cast<uint32_t*>(blk + warp * 4096 + lane * 4);
    pend_mode = 1;
  }
  __device__ __forceinline__ void add_out(const float (&acc)[64], int s, const CUtensorMap* tm, int col, int row) {
    const uint32_t dst = full0 - (NSLOT - s) * SLOT + (wg * 4 + warp) * 4096;
    const uint32_t a = dst + (lane & 15) * 128 + (((lane >> 4) ^ (lane & 7)) << 4);
#pragma unroll
    for (int m = 0; m < 8; m++)
      asm volatile("stmatrix.sync.aligned.m8n8.x4.shared.b16 [%0], {%1, %2, %3, %4};" ::"r"((a ^ ((m & 3) << 5)) + (m >> 2) * 2048),
                   "r"(pack_bf16(acc[8 * m], acc[8 * m + 1])), "r"(pack_bf16(acc[8 * m + 2], acc[8 * m + 3])),
                   "r"(pack_bf16(acc[8 * m + 4], acc[8 * m + 5])), "r"(pack_bf16(acc[8 * m + 6], acc[8 * m + 7]))
                   : "memory");
    asm volatile("fence.proxy.async.shared::cta;" ::: "memory");
    __syncwarp();
    asm volatile(
        "{\n .reg .pred p;\n setp.eq.u32 p, %5, 0;\n"
        " @p cp.reduce.async.bulk.tensor.2d.global.shared::cta.add.tile.bulk_group [%0, {%2, %4}], [%1];\n"
        " @p cp.reduce.async.bulk.tensor.2d.global.shared::cta.add.tile.bulk_group [%0, {%3, %4}], [%1 + 2048];\n"
        " @p cp.async.bulk.commit_group;\n}" ::"l"(tm),
        "r"(dst), "r"(col), "r"(col + 64), "r"(row), "r"(lane)
        : "memory");
  }
  template <int Q>
  __device__ __forceinline__ void flush_quarter(const uint32_t (&pk)[32]) {
    if (pend_mode == 1) {
#pragma unroll
      for (int i = 11 * Q; i < 11 * Q + 11 && i < 32; i++) pend[(i >> 1) * 32 + (i & 1) * 512] = pk[i];
      if (Q == 3) signal();
    }
    if (Q == 3) pend_mode = 0;
  }
  __device__ __forceinline__ void flush_all(const uint32_t (&pk)[32]) {
    flush_quarter<0>(pk);
    flush_quarter<1>(pk);
    flush_quarter<2>(pk);
    flush_quarter<3>(pk);
  }
};

__device__ __forceinline__ int wrap7(int s) { return s >= NSLOT ? s - NSLOT : s; }

__device__ __forceinline__ void mma_chunk_sw(float (&acc)[64], uint32_t a16, uint32_t b16, bool accum) {
#pragma unroll
  for (int kk = 0; kk < 8; kk++)
    wgmma_ss<1>(acc, (a16 + (kk >> 2) * 512 + (kk & 3) * 2) | DESC_SWK_LO, DESC_SW_HI, (b16 + kk * 128) | DESC_SWN_LO, DESC_SW_HI,
                (kk > 0) || accum);
}
__device__ __forceinline__ void mma_chunk_ns(float (&acc)[64], uint32_t a16, uint32_t b16, bool accum) {
#pragma unroll
  for (int kk = 0; kk < 8; kk++)
    wgmma_ss<1>(acc, (a16 + kk * 16) | DESC_NSK_LO, DESC_NSK_HI, (b16 + kk * 128) | DESC_SWN_LO, DESC_SW_HI, (kk > 0) || accum);
}

__device__ __forceinline__ void pack_frag(uint32_t (&P)[32], const float (&S)[64]) {
#pragma unroll
  for (int i = 0; i < 32; i++) P[i] = pack_bf16(S[2 * i], S[2 * i + 1]);
}

__device__ __forceinline__ int ln_row() { return blockIdx.x * 16 + (threadIdx.x >> 4); }
__device__ __forceinline__ void ln_load(const Params& P, uint32_t (&v)[32]) {
  const uint4* a = reinterpret_cast<const uint4*>(P.x) + ln_row() * 64 + (threadIdx.x & 15);
#pragma unroll
  for (int i = 0; i < 4; i++)
    asm volatile("ld.global.nc.v4.u32 {%0, %1, %2, %3}, [%4];"
                 : "=r"(v[4 * i]), "=r"(v[4 * i + 1]), "=r"(v[4 * i + 2]), "=r"(v[4 * i + 3])
                 : "l"(a + 16 * i));
}
__device__ __forceinline__ void ln_sums(const Params& P, uint32_t (&v)[32]) {
  uint4* o = reinterpret_cast<uint4*>(P.out) + ln_row() * 64 + (threadIdx.x & 15);
  const float p = bf_lo(__shfl_sync(0xffffffffu, v[0], 0, 16));
#pragma unroll
  for (int k = 0; k < 4; k++) o[16 * k] = make_uint4(v[4 * k], v[4 * k + 1], v[4 * k + 2], v[4 * k + 3]);
  float s = 0.f, q = 0.f, s1 = 0.f, q1 = 0.f;
#pragma unroll
  for (int i = 0; i < 16; i++) {
    const float x0 = bf_lo(v[i]) - p, x1 = bf_hi(v[i]) - p;
    s += x0;
    s1 += x1;
    q += x0 * x0;
    q1 += x1 * x1;
  }
  v[16] = __float_as_uint(s + s1);
  v[17] = __float_as_uint(q + q1);
  v[18] = __float_as_uint(p);
}
__device__ __forceinline__ void ln_moments(uint32_t (&v)[32]) {
  float s = __uint_as_float(v[16]), q = __uint_as_float(v[17]);
#pragma unroll
  for (int k = 0; k < 4; k++) {
    s += __shfl_xor_sync(0xffffffffu, s, 1 << k);
    q += __shfl_xor_sync(0xffffffffu, q, 1 << k);
  }
  s *= 1.0f / DM;
  q = bf16_round(bf16_round(fmaxf(q * (1.0f / DM) - s * s, 0.f)) + 1e-5f);
  asm("sqrt.approx.ftz.f32 %0, %0;" : "+f"(q));
  q = bf16_round(q);
  asm("rcp.approx.ftz.f32 %0, %0;" : "+f"(q));
  v[16] = __float_as_uint(bf16_round(__uint_as_float(v[18]) + s));
  v[17] = __float_as_uint(q);
}
__device__ __forceinline__ void ln_store(uint32_t (&v)[32]) {
  const int row = ln_row(), c = threadIdx.x & 15;
  uint8_t* d = g_xn + (row >> 6) * BLK + (row & 63) * 128 + (c & 8) * 1024 + (((c ^ row) & 7) << 4);
  const float mb = __uint_as_float(v[16]), rs = __uint_as_float(v[17]);
#pragma unroll
  for (int k = 0; k < 4; k++) {
#pragma unroll
    for (int j = 4 * k; j < 4 * k + 4; j++) {
      const uint32_t t = pack_bf16(bf_lo(v[j]) - mb, bf_hi(v[j]) - mb);
      v[j] = pack_bf16(bf_lo(t) * rs, bf_hi(t) * rs);
    }
    *reinterpret_cast<uint4*>(d + k * 32 * BLK) = make_uint4(v[4 * k], v[4 * k + 1], v[4 * k + 2], v[4 * k + 3]);
  }
}

__device__ __forceinline__ uint8_t* proj_dst(int asrc, int ct, int strip) {
  return asrc ? g_act + (size_t)((NH + ct) * 32 + strip) * BLK : ((ct & 1) ? g_V : g_K) + (size_t)((ct >> 1) * 32 + strip) * BLK;
}
__device__ __forceinline__ void proj_pack(Cons& c, uint32_t (&pk)[32], float (&acc)[64], int asrc, int ct, int strip) {
  fence_regs(acc);
  if (asrc == 0) {
    pack_frag(pk, acc);
  } else {
#pragma unroll
    for (int i = 0; i < 32; i++) pk[i] = pack_bf16_relu(acc[2 * i], acc[2 * i + 1]);
  }
  c.set_pend(proj_dst(asrc, ct, strip));
}
template <int Q>
__device__ __forceinline__ void store_third(uint32_t* dst, const float (&acc)[64], uint32_t lo) {
#pragma unroll
  for (int i = 11 * Q; i < 11 * Q + 11 && i < 32; i++) {
    uint32_t v = pack_bf16(acc[2 * i], acc[2 * i + 1]);
    asm("max.NaN.bf16x2 %0, %0, %1;" : "+r"(v) : "r"(lo));
    dst[(i >> 1) * 32 + (i & 1) * 512] = v;
  }
}

__device__ __forceinline__ void proj_consumer(Cons& c, uint32_t (&pk)[32], const Params& P, uint32_t item, int rank) {
  const int asrc = (item >> 3) & 1, s = (item >> 4) & 7;
  const int start = (item >> 8) & 255, count = item >> 24;
  const int strip = 4 * s + 2 * rank + c.wg;
  const int a0 = c.ptr;
  int bi = 0;
  float acc[64], acc1[64];
#pragma unroll 1
  for (int ch = 0; ch < 4; ch++) {
    const int as = wrap7(a0 + ch), b0 = wrap7(a0 + 4 + bi);
    bi = (bi == 2) ? 0 : bi + 1;
    const int b1 = wrap7(a0 + 4 + bi);
    bi = (bi == 2) ? 0 : bi + 1;
    const uint32_t aa = c.uaddr(as) + c.wg * 1024;
    const int step = 2 * ch + 8 * asrc;
    c.wait_full(as);
    TR3(threadIdx.x == 0 && !asrc, 8 + 3 * ch)
    c.wait_full(b0);
    TR3(threadIdx.x == 0 && !asrc, 9 + 3 * ch)
    c.turn_begin();
    wg_fence();
    mma_chunk_sw(acc, aa, c.uaddr(b0), ch > 0);
    wg_commit();
    c.turn_end();
    if (step == 0) ln_load(P, pk);
    if (step == 4) ln_moments(pk);
    if (step == 6) c.signal();
    if (step == 8) c.flush_quarter<0>(pk);
    if (step == 10) c.flush_quarter<2>(pk);
    const bool ok = c.probe(b1);
    c.mma_wait<0>();
    c.release(b0);
    c.finish(b1, ok);
    TR3(threadIdx.x == 0 && !asrc, 10 + 3 * ch)
    c.turn_begin();
    wg_fence();
    mma_chunk_sw(acc1, aa, c.uaddr(b1), ch > 0);
    wg_commit();
    c.turn_end();
    if (step == 2) ln_sums(P, pk);
    if (step == 4) ln_store(pk);
    if (step == 8) c.flush_quarter<1>(pk);
    if (step == 10) c.flush_quarter<3>(pk);
    if (ch == 3) proj_pack(c, pk, acc, asrc, P.tile[start], strip);
    c.mma_wait<0>();
    c.release(b1);
  }
  TR3(threadIdx.x == 0 && !asrc, 20)
  fence_regs(acc1);
#pragma unroll 1
  for (int u = 8; u < 4 * count; u++) {
    const int ch = u & 3;
    const int as = wrap7(a0 + ch), bs = wrap7(a0 + 4 + bi);
    bi = (bi == 2) ? 0 : bi + 1;
    const uint32_t aa = c.uaddr(as) + c.wg * 1024, ba = c.uaddr(bs);
    c.wait_full(bs);
    c.turn_begin();
    wg_fence();
    mma_chunk_sw(acc, aa, ba, ch > 0);
    wg_commit();
    c.turn_end();
    if (ch == 0) c.flush_quarter<0>(pk);
    if (ch == 1) c.flush_quarter<1>(pk);
    if (ch == 2) c.flush_quarter<2>(pk);
    if (ch == 3) {
      c.flush_quarter<3>(pk);
      uint32_t* dst = reinterpret_cast<uint32_t*>(proj_dst(asrc, P.tile[start + 1], strip) + c.warp * 4096 + c.lane * 4);
      const uint32_t lo = asrc ? 0u : 0xff80ff80u;
      if (u == 11) store_third<0>(dst, acc1, lo);
      if (u == 15) store_third<1>(dst, acc1, lo);
      if (u == 19) store_third<2>(dst, acc1, lo);
    }
    const int ct = P.tile[start + (u >> 2)];
    c.mma_wait<0>();
    c.release(bs);
    if (u >= 4 * count - 4) c.release(as);
    if (ch == 3) {
      TR3(threadIdx.x == 0 && u < 16 && !asrc, 19 + (u >> 2))
      proj_pack(c, pk, acc, asrc, ct, strip);
    }
  }
}

#define SPL 6
#define EXA 4
constexpr float SM_SCALE = 0.08838834764831845f * 1.4426950408889634f;

template <int J0, int J1>
__device__ __forceinline__ void apply_mask(float (&S)[64], int d) {
#pragma unroll
  for (int j = J0; j < J1; j++) {
    const int c = 8 * (j - J0);
    if (c > d) S[4 * j] = -INFINITY;
    if (c + 1 > d) S[4 * j + 1] = -INFINITY;
    if (c - 8 > d) S[4 * j + 2] = -INFINITY;
    if (c - 7 > d) S[4 * j + 3] = -INFINITY;
  }
}

template <int J0, int J1, bool INIT>
__device__ __forceinline__ void exp_part(float (&D)[64], const float (&S)[64], float (&t)[4]) {
#pragma unroll
  for (int j = J0; j < J1; j++) {
#pragma unroll
    for (int i = 0; i < 4; i++) {
      D[4 * j + i] = ex2(S[4 * j + i]);
      t[i] = (INIT && j == J0) ? D[4 * j + i] : t[i] + D[4 * j + i];
    }
  }
}
constexpr float P_MAX = 1152921504606846976.0f;
constexpr float P_MIN = 8.673617379884035e-19f;

template <int K0, int K1>
__device__ __forceinline__ void mma_qk(float (&S)[64], const uint32_t (&Q)[32], uint32_t k16) {
#pragma unroll
  for (int kk = K0; kk < K1; kk++)
    wgmma_rs<0>(S, Q[4 * kk], Q[4 * kk + 1], Q[4 * kk + 2], Q[4 * kk + 3], (k16 + kk * 16) | DESC_NSK_LO, DESC_NSK_HI, kk > 0);
}
template <int H>
__device__ __forceinline__ void mma_qk_half(float (&S)[64], const uint32_t (&Q)[32], uint32_t k16) {
#pragma unroll
  for (int kk = 0; kk < 8; kk++)
    wgmma_rs_n64<H>(S, Q[4 * kk], Q[4 * kk + 1], Q[4 * kk + 2], Q[4 * kk + 3], (k16 + kk * 16) | DESC_NSK_LO, DESC_NSK_HI, kk > 0);
}
template <int K0, int K1>
__device__ __forceinline__ void mma_pv(float (&O)[64], const uint32_t (&P)[32], uint32_t v16, bool accum) {
#pragma unroll
  for (int kk = K0; kk < K1; kk++)
    wgmma_rs<1>(O, P[4 * kk], P[4 * kk + 1], P[4 * kk + 2], P[4 * kk + 3], (v16 + kk * 256) | DESC_NSN_LO, DESC_NSN_HI,
                (kk > K0) || accum);
}

__device__ __forceinline__ int attn_strip(int rank, bool is_long) { return is_long ? 3 - rank : rank; }

__device__ __forceinline__ uint32_t ld_l2(const uint8_t* p) {
  uint32_t v;
  asm volatile("ld.relaxed.gpu.global.u32 %0, [%1];" : "=r"(v) : "l"(p) : "memory");
  return v;
}
__device__ __forceinline__ void mma_warp(float* d, const uint32_t* a, uint32_t b0, uint32_t b1) {
  asm volatile("mma.sync.aligned.m16n8k16.row.col.f32.bf16.bf16.f32 {%0,%1,%2,%3}, {%4,%5,%6,%7}, {%8,%9}, {%0,%1,%2,%3};"
               : "+f"(d[0]), "+f"(d[1]), "+f"(d[2]), "+f"(d[3])
               : "r"(a[0]), "r"(a[1]), "r"(a[2]), "r"(a[3]), "r"(b0), "r"(b1));
}
__device__ __forceinline__ void redo_rows(float (&O)[64], const uint32_t (&Q)[32], float (&l)[2], int h, int n, int lane) {
  float m[2] = {-INFINITY, -INFINITY};
  l[0] = l[1] = 0.f;
#pragma unroll
  for (int i = 0; i < 64; i++) O[i] = 0.f;
  const size_t off = (size_t)h * 32 * BLK + lane * 4;
#pragma unroll 1
  for (int kb = 0; kb <= n; kb++) {
    const uint8_t* kp = g_K + off + kb * 4096;
    const uint8_t* vp = g_V + off + kb * 4096;
    float s[8] = {0.f, 0.f, 0.f, 0.f, 0.f, 0.f, 0.f, 0.f}, sc[2];
#pragma unroll
    for (int i = 0; i < 16; i++)
      mma_warp(s + 4 * (i & 1), Q + 4 * (i >> 1), ld_l2(kp + (i & 1) * 2048 + (i >> 1) * 256), ld_l2(kp + (i & 1) * 2048 + (i >> 1) * 256 + 128));
    const int d = (n - kb) * 16 + (lane >> 2) - (lane & 3) * 2;
#pragma unroll
    for (int i = 0; i < 8; i++)
      if ((i >> 2) * 8 + (i & 1) - (i & 2) * 4 > d) s[i] = -INFINITY;
#pragma unroll
    for (int r = 0; r < 2; r++) {
      float a = fmaxf(fmaxf(s[2 * r], s[2 * r + 1]), fmaxf(s[2 * r + 4], s[2 * r + 5]));
      a = fmaxf(a, __shfl_xor_sync(0xffffffffu, a, 1));
      a = fmaxf(fmaxf(a, __shfl_xor_sync(0xffffffffu, a, 2)), m[r]);
      sc[r] = ex2(m[r] - a);
      m[r] = a;
      l[r] *= sc[r];
    }
    uint32_t p[4];
#pragma unroll
    for (int i = 0; i < 4; i++) {
      const float e0 = ex2(s[2 * i] - m[i & 1]), e1 = ex2(s[2 * i + 1] - m[i & 1]);
      l[i & 1] += e0 + e1;
      p[i] = pack_bf16(e0, e1);
    }
#pragma unroll
    for (int i = 0; i < 16; i++) {
      uint32_t b0 = ld_l2(vp + i * 128), b1 = ld_l2(vp + i * 128 + 2048);
      asm volatile("movmatrix.sync.aligned.m8n8.trans.b16 %0, %0;" : "+r"(b0));
      asm volatile("movmatrix.sync.aligned.m8n8.trans.b16 %0, %0;" : "+r"(b1));
#pragma unroll
      for (int k = 0; k < 4; k++) O[4 * i + k] *= sc[k >> 1];
      mma_warp(O + 4 * i, p, b0, b1);
    }
  }
}

__device__ __forceinline__ void quad_sum(float (&l)[2]) {
#pragma unroll
  for (int k = 1; k < 4; k *= 2) {
    l[0] += __shfl_xor_sync(0xffffffffu, l[0], k);
    l[1] += __shfl_xor_sync(0xffffffffu, l[1], k);
  }
}
__device__ __forceinline__ void invert(float (&l)[2]) {
  asm volatile("rcp.approx.ftz.f32 %0, %0;" : "+f"(l[0]));
  asm volatile("rcp.approx.ftz.f32 %0, %0;" : "+f"(l[1]));
}
__device__ __forceinline__ void pack_scaled(uint32_t (&P)[32], const float (&O)[64], const float (&f)[2]) {
#pragma unroll
  for (int i = 0; i < 32; i++) P[i] = pack_bf16(O[2 * i] * f[i & 1], O[2 * i + 1] * f[i & 1]);
}
template <int J0, int J1>
__device__ __forceinline__ void hold(const Cons& c, float (&S)[64]) {
  if (c.full0 == 0) {
#pragma unroll
    for (int j = J0; j < J1; j++)
      asm volatile("ld.shared.v4.f32 {%0, %1, %2, %3}, [%4];" : "=f"(S[4 * j]), "=f"(S[4 * j + 1]), "=f"(S[4 * j + 2]), "=f"(S[4 * j + 3]) : "r"(16 * j));
  }
}

__device__ __forceinline__ void attn_consumer(Cons& c, uint32_t (&P)[32], uint32_t& item, int& ii, uint32_t ibuf, int rank, int& role) {
  const int diag = c.warp * 16 + (c.lane >> 2) - (c.lane & 3) * 2;
  float S[64], O[64];
  uint32_t Q[32];
  float l[2];
  role = __shfl_sync(0xffffffffu, role, 0);
  int ch = 0;
  while (true) {
    const int J = (item >> 4) & 7, h = (item >> 8) & 255;
    const bool is_long = (role == c.wg);
    const int strip = attn_strip(rank, is_long);
    const int nb = 2 * J + (is_long ? 2 : 1);
    const bool half = !(strip & 1);
    const int rcount = is_long ? 2 : 1;
    role ^= 1;
    ii++;
    const int xs = (c.ptr + 4 * J + 12 - 2 * ch) % NSLOT, ws = wrap7(xs + 1), vl = wrap7(xs + (is_long ? 6 : 5));
    const uint32_t skipped = is_long ? 0u : (1u << wrap7(xs + 4)) | (1u << wrap7(xs + 6));
#pragma unroll 1
    for (; ch < 4; ch++) {
      const int as = c.next(), bs = c.next();
      const uint32_t aa = c.uaddr(as) + c.wg * 1024, ba = c.uaddr(bs);
      c.wait_full(as);
      c.wait_full(bs);
      c.turn_begin();
      wg_fence();
      mma_chunk_sw(S, aa, ba, ch > 0);
      wg_commit();
      c.turn_end();
      if (ch == 0) c.flush_quarter<0>(P);
      if (ch == 1) c.flush_quarter<1>(P);
      if (ch == 2) c.flush_quarter<2>(P);
      if (ch == 3) c.flush_quarter<3>(P);
      c.mma_wait<0>();
      c.release(as);
      c.release(bs);
    }
    ch = 1;
    fence_regs(S);
#pragma unroll
    for (int i = 0; i < 32; i++) Q[i] = pack_bf16(S[2 * i] * SM_SCALE, S[2 * i + 1] * SM_SCALE);
    fence_regs(Q);
    int kn, vn;
    {
      const int kc = c.next();
      kn = c.next();
      vn = c.next();
      const uint32_t ka = c.uaddr(kc), kb = c.uaddr(kn);
      c.wait_full(kc);
      float t[4];
      if (nb > 1) {
        c.turn_begin();
        wg_fence();
        mma_qk<0, 8>(O, Q, ka);
        wg_commit();
        c.wait_full(kn);
        wg_fence();
        mma_qk<0, SPL>(S, Q, kb);
        wg_commit();
        c.mma_wait<1>();
        c.release(kc);
        fence_regs(O);
        exp_part<0, EXA, true>(O, O, t);
        fence_regs(O);
        wg_fence();
        mma_qk<SPL, 8>(S, Q, kb);
        wg_commit();
        c.turn_end();
        const bool vok = c.probe(vn);
        hold<EXA, 16>(c, O);
        exp_part<EXA, 12, false>(O, O, t);
        fence_regs(O);
        fence_regs(t);
        c.finish(vn, vok);
        c.mma_wait<0>();
        c.release(kn, nb == 2 ? 2 : 1);
        fence_regs(S);
      } else {
        c.turn_begin();
        wg_fence();
        mma_qk<0, 8>(O, Q, ka);
        wg_commit();
        c.turn_end();
        c.wait_full(vn);
        item = __shfl_sync(0xffffffffu, wait_item(ibuf + 4 * ii), 0);
        c.mma_wait<0>();
        c.release(kc);
        fence_regs(O);
        apply_mask<0, 16>(O, diag + (strip & 1) * 64);
        exp_part<0, 12, true>(O, O, t);
      }
      c.pend = reinterpret_cast<uint32_t*>(g_act + (size_t)(h * 32 + 4 * J + strip) * BLK + c.warp * 4096 + c.lane * 4);
      exp_part<12, 16, false>(O, O, t);
      pack_frag(P, O);
      fence_regs(P);
      l[0] = t[0] + t[1];
      l[1] = t[2] + t[3];
    }
    if (nb > 1) {
      auto turn = [&](bool both, int count, auto&& idle) {
        const uint32_t ka = c.uaddr(kn), va = c.uaddr(vn);
        if (both) {
          c.turn_begin();
          wg_fence();
          mma_qk<0, 8>(S, Q, ka);
          wg_commit();
          mma_pv<0, SPL>(O, P, va, true);
          wg_commit();
          const int kc = kn;
          idle();
          c.mma_wait<1>();
          c.release(kc, count);
          fence_regs(S);
        } else {
          c.turn_begin();
          wg_fence();
          mma_pv<0, SPL>(O, P, va, false);
          wg_commit();
          idle();
        }
      };
      auto turn_rest = [&](int pv) {
        const uint32_t va = c.uaddr(pv);
        fence_regs(S);
        wg_fence();
        mma_pv<SPL, 8>(O, P, va, true);
        wg_commit();
        c.turn_end();
      };
#pragma unroll 1
      for (int j = 1; j + 1 < nb; j++) {
        const int pv = vn;
        bool kok, vok;
        turn(j > 1, 1, [&]() {
          kn = c.next();
          vn = c.next();
          kok = c.probe(kn);
          vok = c.probe(vn);
        });
        float t[4];
        exp_part<0, EXA, true>(S, S, t);
        turn_rest(pv);
        hold<EXA, 16>(c, S);
        exp_part<EXA, 12, false>(S, S, t);
        fence_regs(S);
        fence_regs(t);
        c.finish(kn, kok);
        c.finish(vn, vok);
        c.mma_wait<0>();
        c.release(pv);
        fence_regs(O);
        fence_regs(P);
        exp_part<12, 16, false>(S, S, t);
        pack_frag(P, S);
        fence_regs(P);
        l[0] += t[0] + t[1];
        l[1] += t[2] + t[3];
      }
      turn(nb > 2, rcount, [&]() { item = __shfl_sync(0xffffffffu, wait_item(ibuf + 4 * ii), 0); });
      float t[4];
      if (half) apply_mask<0, EXA>(S, diag);
      exp_part<0, EXA, true>(S, S, t);
      turn_rest(vn);
      const bool ok = c.probe(vl) & (c.probe(xs) & c.probe(ws) | ((item & 7) != IT_ATTN));
      hold<EXA, 16>(c, S);
      if (half) {
        apply_mask<EXA, 8>(S, diag - 8 * EXA);
        exp_part<EXA, 8, false>(S, S, t);
      } else {
        apply_mask<8, 16>(S, diag);
        exp_part<EXA, 12, false>(S, S, t);
      }
      fence_regs(S);
      c.finish_all((1u << vl) | ((item & 7) == IT_ATTN ? (1u << xs) | (1u << ws) : 0u), ok);
      c.mma_wait<0>();
      c.release(vn);
      fence_regs(O);
      fence_regs(P);
      if (half) {
#pragma unroll
        for (int i = 0; i < 16; i++) P[i] = pack_bf16(S[2 * i], S[2 * i + 1]);
      } else {
        exp_part<12, 16, false>(S, S, t);
        pack_frag(P, S);
      }
      fence_regs(P);
      l[0] += t[0] + t[1];
      l[1] += t[2] + t[3];
    } else if ((item & 7) == IT_ATTN) {
      c.wait_full(xs);
      c.wait_full(ws);
    }
    c.ph ^= skipped;
    const uint32_t va = c.uaddr(vl), aa = c.uaddr(xs) + c.wg * 1024, ba = c.uaddr(ws);
    const bool more = (item & 7) == IT_ATTN;
    bool redo;
    auto sums = [&]() {
      c.turn_end();
      quad_sum(l);
      redo = __any_sync(0xffffffffu, !((fmaxf(l[0], l[1]) <= P_MAX) & (l[0] >= P_MIN) & (l[1] >= P_MIN)));
      invert(l);
    };
    auto result = [&]() {
      c.release(vl, rcount);
      fence_regs(O);
      fence_regs(P);
      pack_scaled(P, O, l);
      c.pend_mode = 1;
    };
    c.turn_begin();
    wg_fence();
    mma_pv<0, 4>(O, P, va, nb > 1);
    wg_commit();
    if (!half) {
      wg_fence();
      mma_pv<4, 8>(O, P, va, true);
      wg_commit();
    }
    if (more) {
      wg_fence();
      mma_chunk_sw(S, aa, ba, false);
      wg_commit();
      sums();
      c.mma_wait<1>();
      result();
      c.flush_quarter<0>(P);
      c.mma_wait<0>();
      c.release(xs);
      c.release(ws);
      fence_regs(S);
    } else {
      sums();
      c.mma_wait<0>();
      result();
    }
    if (__builtin_expect(redo, 0)) {
      redo_rows(O, Q, l, h, (4 * J + strip) * 4 + c.warp, c.lane);
      quad_sum(l);
      invert(l);
      pack_scaled(P, O, l);
      c.flush_quarter<0>(P);
    }
    fence_regs(P);
    if (!more) {
      c.ptr = xs;
      return;
    }
    TRACE_ITEM
    c.ptr = wrap7(xs + 2);
  }
}

__device__ __forceinline__ bool out_consumer(Cons& c, uint32_t (&pk)[32], const Params& P, uint32_t& item, uint32_t next_addr, int rank,
                                             int leader) {
  const int J = (item >> 4) & 7, half = (item >> 3) & 1, count = item >> 24;
  const int row = (4 * J + 2 * rank + c.wg) * 64 + c.warp * 16;
  float acc0[64], acc1[64];
  if (!__shfl_sync(0xffffffffu, (int)c.probe(c.ptr), 0)) c.flush_all(pk);
#pragma unroll 1
  for (int ch = 0; ch < count - 2; ch++) {
    const int as = c.next(), b0 = c.next();
    const uint32_t aa = c.uaddr(as) + c.wg * 1024, ba = c.uaddr(b0);
    if (ch == 1 && !__shfl_sync(0xffffffffu, (int)c.probe(as), 0)) c.flush_quarter<3>(pk);
    c.wait_full(as);
    c.wait_full(b0);
    c.turn_begin();
    wg_fence();
    mma_chunk_ns(acc0, aa, ba, ch > 0);
    wg_commit();
    c.turn_end();
    if (ch == 0) {
      c.flush_quarter<0>(pk);
      c.flush_quarter<1>(pk);
    }
    if (ch == 1) c.flush_quarter<3>(pk);
    const int b1 = c.next();
    const uint32_t bb = c.uaddr(b1);
    c.wait_full(b1);
    c.mma_wait<0>();
    c.release(b0);
    c.turn_begin();
    wg_fence();
    mma_chunk_ns(acc1, aa, bb, ch > 0);
    wg_commit();
    c.turn_end();
    if (ch == 0) c.flush_quarter<2>(pk);
    c.mma_wait<0>();
    if (ch < count - 3) c.release(b1);
    c.release(as);
  }
  const int s0 = c.ptr;
  c.wait_full(s0);
  c.wait_full(wrap7(s0 + 1));
#pragma unroll 1
  for (int i = 0; i < 4; i += 2) {
    c.turn_begin();
    wg_fence();
    mma_chunk_ns(acc0, c.uaddr(wrap7(s0 + i)) + c.wg * 1024, c.uaddr(wrap7(s0 + i + 1)), true);
    wg_commit();
    c.turn_end();
    c.wait_full(wrap7(s0 + i + 2));
    if (i == 0) c.wait_full(wrap7(s0 + 3));
    else item = __shfl_sync(0xffffffffu, wait_item(next_addr), 0);
    c.mma_wait<0>();
  }
  fence_regs(acc0);
  T5(0)
  const bool last = item == IT_END;
#pragma unroll 1
  for (int i = 0; i < 2; i++) {
    c.turn_begin();
    wg_fence();
    mma_chunk_ns(acc1, c.uaddr(wrap7(s0 + 2 * i)) + c.wg * 1024, c.uaddr(wrap7(s0 + 4 + i)), true);
    wg_commit();
    if (i == 0 || !last || c.wg == leader) c.turn_end();
    if (i == 0) {
      T5(1)
      c.wait_full(wrap7(s0 + 5));
      c.add_out(acc0, wrap7(s0 + 6), &P.tm_out, half * 256, row);
      T5(2)
    } else if (last) {
      c.leave();
    }
    c.mma_wait<0>();
  }
  fence_regs(acc1);
  T5(3)
  c.add_out(acc1, s0, &P.tm_out, half * 256 + 128, row);
  T5(4)
  asm volatile("cp.async.bulk.wait_group.read 0;" ::: "memory");
  T5(5)
  if (last) return true;
  asm volatile("bar.sync %0, 128;" ::"r"(3 + c.wg) : "memory");
  c.ptr = wrap7(s0 + 6);
#pragma unroll 1
  for (int s = 0; s < NSLOT; s++) c.release(s);
  return false;
}

struct Prod {
  uint32_t base, full0, empty0, ph;
  int ptr;
  __device__ __forceinline__ int next() {
    int s = ptr;
    ptr = (ptr == NSLOT - 1) ? 0 : ptr + 1;
    return s;
  }
  __device__ __forceinline__ void stamp(uint32_t) {}
  __device__ __forceinline__ void acquire(int s) {
    stamp(8);
    mbar_wait(empty0 + 8 * s, ((ph >> s) & 1) ^ 1);
    stamp(s);
    ph ^= 1u << s;
    mbar_expect_tx(full0 + 8 * s, SLOT);
  }
  __device__ __forceinline__ uint32_t addr(int s) const { return base + s * SLOT; }
  __device__ __forceinline__ uint32_t bar(int s) const { return full0 + 8 * s; }
  __device__ __forceinline__ void load_xn(int s, int strip0, int strip1, int ch) {
    acquire(s);
    bulk_g2s(addr(s), g_xn + (ch * 32 + strip0) * BLK, BLK, bar(s));
    bulk_g2s(addr(s) + BLK, g_xn + (ch * 32 + strip1) * BLK, BLK, bar(s));
  }
  __device__ __forceinline__ void load_w(int s, const CUtensorMap* tm, int n0, int k0, int rank) {
    acquire(s);
    tma_2d_mc(addr(s) + rank * BLK, tm, n0 + rank * 64, k0, bar(s));
  }
  __device__ __forceinline__ void load_shared_blocks(int s, const uint8_t* src, int rank) {
    acquire(s);
    bulk_g2s_mc(addr(s) + rank * BLK, src + rank * BLK, BLK, bar(s));
  }
  __device__ __forceinline__ void load_own_blocks(int s, const uint8_t* src) {
    acquire(s);
    bulk_g2s(addr(s), src, SLOT, bar(s));
  }
};

__device__ __forceinline__ uint32_t dep_peek(int idx, uint32_t full, uint32_t ep) {
  const uint32_t v = ld_acquire(&g_flags[idx * FL_STRIDE]);
  asm volatile("fence.proxy.async.global;" ::: "memory");
  return (v - (ep - 1) * full) & full;
}
__device__ __forceinline__ void dep_need(uint32_t& ready, int n, int idx, uint32_t full, uint32_t ep) {
  while (!((ready >> (4 * n)) & 15)) {
    __nanosleep(40);
    ready = dep_peek(idx, full, ep);
  }
}

__device__ __forceinline__ void producer(const Params& P, Prod& p, uint32_t ibuf, int rank) {
  uint32_t ep;
  asm volatile("ld.relaxed.gpu.global.u32 %0, [%1];" : "=r"(ep) : "l"(&g_epoch[blockIdx.x]) : "memory");
  TR3(true, 3)
  ep += 1;
  bool xn_ok = false;
  auto need_xn = [&]() {
    if (!xn_ok) {
      mbar_wait(p.full0 + 152, 0);
      asm volatile("fence.proxy.async.global;" ::: "memory");
      xn_ok = true;
    }
  };
  for (int ii = 0;; ii++) {
    const uint32_t item = wait_item(ibuf + 4 * ii);
    const int type = item & 7;
    if (type == IT_END) break;
    p.stamp(8 + type);
    auto claim = [&]() { mbar_arrive_local(p.full0 + 144); };
    const int J = (item >> 4) & 7;
    if (type == IT_PROJ) {
      const int asrc = (item >> 3) & 1;
      const int start = (item >> 8) & 255, count = item >> 24;
      if (asrc) need_xn();
      const int a0 = p.ptr;
      int bi = asrc ? 0 : 2;
      if (!asrc) mbar_wait(p.empty0 + 8 * 6, 0);
#pragma unroll 1
      for (int u = asrc ? 0 : 8; u < 4 * count; u++) {
        const int t = u < 8 ? u & 1 : u >> 2, ch = u < 8 ? u >> 1 : u & 3;
        if (u == 4 * count - 4) claim();
        if (t == 0) p.load_own_blocks(wrap7(a0 + ch), g_xn + (ch * 32 + 4 * J + 2 * rank) * BLK);
        const int ct = P.tile[start + t];
        p.load_w(wrap7(a0 + 4 + bi), asrc ? &P.tm_w1 : ((ct & 1) ? &P.tm_wuv : &P.tm_wuk), (asrc ? ct : ct >> 1) * 128, ch * 128, rank);
        TR3(ii == 0 && u < 10, 24 + u)
        bi = (bi == 2) ? 0 : bi + 1;
        if (ch == 1 && !xn_ok && mbar_test(p.full0 + 152, 0)) need_xn();
        const int tp = u < 2 ? u : (u >> 2) + 2;
        if (rank == (J & 1) && (u < 2 || (u & 3) == 3) && tp < count) {
          const int cp = P.tile[start + tp];
          tma_prefetch(asrc ? &P.tm_w1 : ((cp & 1) ? &P.tm_wuv : &P.tm_wuk), (asrc ? cp : cp >> 1) * 128 + rank * 64, (J >> 1) * 128);
        }
      }
    } else if (type == IT_ATTN) {
      const int h = (item >> 8) & 255;
      need_xn();
      const int s0 = 4 * J + attn_strip(rank, !(p.ph & 128)), s1 = s0 ^ 3;
      p.ph ^= 128;
      uint32_t ready = 0;
#pragma unroll 1
      for (int ch = 0; ch < 4; ch++) {
        p.load_xn(p.next(), s0, s1, ch);
        p.load_w(p.next(), &P.tm_wq, h * 128, ch * 128, rank);
        if (ch == 0) ready = dep_peek(FL_KV + h, 0x88888888u, ep);
      }
      const uint8_t* kp = g_K + (size_t)h * 32 * BLK;
      const uint8_t* vp = g_V + (size_t)h * 32 * BLK;
      const int n = 2 * J + 2;
#pragma unroll 1
      for (int j = 0; j < n; j++) {
        dep_need(ready, j >> 1, FL_KV + h, 0x88888888u, ep);
        p.load_shared_blocks(p.next(), kp + (size_t)j * SLOT, rank);
        if (j == n - 1) claim();
        if (j > 0) p.load_shared_blocks(p.next(), vp + (size_t)(j - 1) * SLOT, rank);
      }
      p.load_shared_blocks(p.next(), vp + (size_t)(n - 1) * SLOT, rank);
    } else {
      const int half = (item >> 3) & 1, start = (item >> 8) & 255, count = item >> 24;
      uint32_t ready = 0;
#pragma unroll 1
      for (int i = 0; i < count; i++) {
        const int pos = start + i, ck = P.order[J][pos];
        const uint32_t full = pos < 40 ? 0x44444444u : 0x444444u;
        if (i == 0 || (pos & 7) == 0) ready = dep_peek(FL_ACT + J * 6 + (pos >> 3), full, ep);
        dep_need(ready, pos & 7, FL_ACT + J * 6 + (pos >> 3), full, ep);
        const CUtensorMap* tw = ck < NH ? &P.tm_wo : &P.tm_w2;
        const int k0 = (ck < NH ? ck : ck - NH) * 128;
        if (i == count - 1) claim();
        p.load_own_blocks(p.next(), g_act + (size_t)(ck * 32 + 4 * J + 2 * rank) * BLK);
        p.load_w(p.next(), tw, half * 256, k0, rank);
        if (i == count - 1) {
          const int cp = P.order[J][pos - 1];
          p.load_w(p.next(), cp < NH ? &P.tm_wo : &P.tm_w2, half * 256 + 128, (cp < NH ? cp : cp - NH) * 128, rank);
        }
        if (i != count - 2) p.load_w(p.next(), tw, half * 256 + 128, k0, rank);
      }
    }
  }
  g_epoch[blockIdx.x] = ep;
}

__device__ __forceinline__ void signaller(const Params& P, uint32_t cnt_addr, uint32_t ibuf, bool early) {
  uint32_t ev = 0;
  auto publish = [&](int idx, int n, bool event = true) {
    if (event) ev += 128;
    uint32_t v;
    while (true) {
      asm volatile("ld.acquire.cta.shared::cta.u32 %0, [%1];" : "=r"(v) : "r"(cnt_addr) : "memory");
      if (v >= ev) break;
      __nanosleep(64);
    }
    asm volatile("fence.acq_rel.gpu;" ::: "memory");
    asm volatile("red.relaxed.gpu.global.add.u32 [%0], %1;" ::"l"(&g_flags[idx * FL_STRIDE]), "r"(1u << (4 * n)) : "memory");
  };
  publish(FL_XN, 0, early);
  for (int ii = 0; ii < MAX_ITEMS; ii++) {
    uint32_t item;
    while (true) {
      asm volatile("ld.volatile.shared.u32 %0, [%1];" : "=r"(item) : "r"(ibuf + 4 * ii) : "memory");
      if (item != 0) break;
      __nanosleep(200);
    }
    const int type = item & 7;
    if (type == IT_END) break;
    const int J = (item >> 4) & 7;
    if (type == IT_PROJ) {
      const int asrc = (item >> 3) & 1;
      const int start = (item >> 8) & 255, count = item >> 24;
      for (int t = 0; t < count; t++) {
        const int ct = P.tile[start + (t == 4 ? 1 : t + (t > 0 && t < 4))];
        const int pos = P.pos[J][asrc ? NH + ct : 0];
        publish(asrc ? FL_ACT + J * 6 + (pos >> 3) : FL_KV + (ct >> 1), asrc ? pos & 7 : J, t != 4);
      }
    } else if (type == IT_ATTN) {
      const int pos = P.pos[J][(item >> 8) & 255];
      publish(FL_ACT + J * 6 + (pos >> 3), pos & 7);
    }
  }
}

#define PFA 3
#define PFW 0x3f201fffu
__global__ void __cluster_dims__(2, 1, 1) __launch_bounds__(384, 1) fused_kernel(const __grid_constant__ Params P) {
  extern __shared__ uint8_t smem_raw[];
  const uint32_t raw = smem_u32(smem_raw);
  const uint32_t base = (raw + 1023) & ~1023u;
  const uint32_t bars = base + NSLOT * SLOT;
  const uint32_t ibuf = bars + 256;
  const int warp_id = __shfl_sync(0xffffffffu, threadIdx.x >> 5, 0);
  const int lane = threadIdx.x & 31;
  const int rank = blockIdx.x & 1;
  const int pair = blockIdx.x >> 1;
  const bool early = pair < 64;
  if (warp_id < 8) {
    cluster_arrive();
  } else {
    const CUtensorMap* tw0 = (pair & 8) ? &P.tm_wuv : &P.tm_wuk;
    if (threadIdx.x == 352) {
      asm volatile("prefetch.tensormap [%0];" ::"l"(&P.tm_ckv) : "memory");
      asm volatile("prefetch.tensormap [%0];" ::"l"(tw0) : "memory");
    }
    asm volatile("setmaxnreg.dec.sync.aligned.u32 40;");
    if (threadIdx.x == 352) {
      for (int i = 0; i < NSLOT; i++) {
        mbar_init(bars + 8 * i, 1);
        mbar_init(bars + 64 + 8 * i, 4);
      }
      mbar_init(bars + 136, 11);
      mbar_init(bars + 144, 1);
      mbar_init(bars + 152, 1);
      asm volatile("st.shared.v2.u32 [%0], {%1, %1};" ::"r"(bars + 128), "r"(0u) : "memory");
      asm volatile("fence.mbarrier_init.release.cluster;" ::: "memory");
      asm volatile("fence.proxy.async.shared::cta;" ::: "memory");
      TR3(true, 0)
    }
    __syncwarp();
    cluster_arrive();
    if (warp_id == 11) {
      const int row0 = (4 * (pair & 7) + 2 * rank) * 64, col0 = (pair >> 4) * 128 + rank * 64;
#pragma unroll 1
      for (int u = 0, b = 0; u < 8; u++, b = b == 2 ? 0 : b + 1) {
        if (early && lane == 0 && !(u & 1)) {
          mbar_expect_tx(bars + 4 * u, SLOT);
#pragma unroll
          for (int i = 0; i < 4; i++)
            tma_2d(base + u * (SLOT / 2) + i * 8192, &P.tm_ckv, u * 64 + (i & 1) * 64, row0 + (i >> 1) * 64, bars + 4 * u);
        }
        __syncwarp();
        if (u == 0) cluster_wait();
        if (early) mbar_wait_bounded(bars + 64 + 8 * (4 + b), (u < 3) | (u > 5));
        if (early && lane == 0) {
          mbar_expect_tx(bars + 8 * (4 + b), SLOT);
          tma_2d_mc(base + (4 + b) * SLOT + rank * BLK, tw0, col0 + (u & 1) * 512, (u >> 1) * 128, bars + 8 * (4 + b));
          if (u == PFA) tma_prefetch(&P.tm_ckv, 256 + ((pair >> 3) & 3) * 64, row0 + (pair >> 5) * 64);
          const int tp = (PFW >> (4 * u)) & 15;
          if (rank == (pair & 1) && tp < 4) tma_prefetch(tw0, col0 + tp * 512, (pair & 6) * 64);
        }
        TR3(lane == 0, 24 + u)
      }
      TR3(lane == 0, 7)
    }
  }
  const uint32_t item0 = P.list[pair];

  if (warp_id >= 8) {
    if (warp_id < 11) {
      if (warp_id == 8)
        asm volatile("st.shared.v4.u32 [%0], {%1, %2, %2, %2};" ::"r"(ibuf + 16 * lane), "r"(lane == 0 ? item0 : 0u), "r"(0u) : "memory");
      asm volatile("bar.sync 0, 352;" ::: "memory");
      TR3(threadIdx.x == 256, 1)
      cluster_wait();
      TR3(threadIdx.x == 256, 2)
    }
    if (lane == 0) {
      if (warp_id == 8) {
        Prod p;
        p.base = base;
        p.full0 = bars;
        p.empty0 = bars + 64;
        p.ph = early ? 0x3f : 0;
        p.ptr = 0;
        producer(P, p, ibuf, rank);
        p.stamp(12);
        mbar_arrive_local(bars + 136);
      } else if (warp_id < 11) {
        signaller(P, bars + 128 + 4 * (warp_id - 9), ibuf, early);
        mbar_arrive_local(bars + 136);
      } else {
        const unsigned long long t0 = globaltimer();
        {
          uint32_t ep;
          asm volatile("ld.relaxed.gpu.global.u32 %0, [%1];" : "=r"(ep) : "l"(&g_epoch[blockIdx.x]) : "memory");
          while ((int32_t)(ld_acquire(&g_flags[FL_XN * FL_STRIDE]) - 2 * NCTA * (ep + 1)) < 0) {
            __nanosleep(100);
            if (globaltimer() - t0 > 2000000000ull) __trap();
          }
          mbar_arrive_local(bars + 152);
        }
        if (rank == 0) {
          const uint32_t ibuf_peer = mapa(ibuf, 1);
          uint32_t nxt = item0;
          for (int ii = 1; nxt != IT_END; ii++) {
            while (!mbar_try_wait(bars + 144, (ii & 1) ^ 1)) {
              if (globaltimer() - t0 > 2000000000ull) __trap();
            }
            uint32_t ticket;
            asm volatile("atom.relaxed.gpu.global.add.u32 %0, [%1], 1;" : "=r"(ticket) : "l"(&g_queue) : "memory");
            const uint32_t idx = ticket + NPAIR;
            nxt = idx < P.n_items ? P.list[idx] : (uint32_t)IT_END;
            if (ii == MAX_ITEMS) __trap();
            asm volatile("st.relaxed.cluster.shared::cluster.u32 [%0], %1;" ::"r"(ibuf_peer + 4 * ii), "r"(nxt) : "memory");
            asm volatile("st.volatile.shared.u32 [%0], %1;" ::"r"(ibuf + 4 * ii), "r"(nxt) : "memory");
            if (ticket == P.n_items - 1) g_queue = 0;
          }
        }
      }
    }
    __syncwarp();
    cluster_arrive();
    if (threadIdx.x == 352) {
      const unsigned long long t0 = globaltimer();
      while (!mbar_try_wait(bars + 136, 0)) {
        if (globaltimer() - t0 > 2000000000ull) __trap();
      }
    }
    __syncwarp();
  } else {
    asm volatile("setmaxnreg.inc.sync.aligned.u32 232;");
    asm volatile("bar.sync 0, 352;" ::: "memory");
    cluster_wait();
    Cons c;
    c.wg = warp_id >> 2;
    c.warp = warp_id & 3;
    c.lane = lane;
    c.slot16 = (base & 0x3FFFF) >> 4;
    c.full0 = bars;
    c.rel0 = mapa(bars + 64, c.warp & 1);
    c.releaser = (lane == 0) && (c.warp < 2);
    c.ph = 0;
    c.ptr = 0;
    c.sigcnt = bars + 128 + 4 * c.wg;
    c.pend = nullptr;
    c.pend_mode = 0;
    uint32_t pk[32];
    int odd = 0;
    if (c.wg == 1) asm volatile("bar.arrive 1, 256;" ::: "memory");
    TR3(threadIdx.x == 0, 5)
    int ii = 0;
    uint32_t item = item0;
#pragma unroll 1
    while (true) {
      c.ptr = __shfl_sync(0xffffffffu, c.ptr, 0);
      c.ph = __shfl_sync(0xffffffffu, c.ph, 0);
      c.pend_mode = __shfl_sync(0xffffffffu, c.pend_mode, 0);
      item = __shfl_sync(0xffffffffu, item, 0);
      const int type = item & 7;
      TRACE_ITEM
      if (type == IT_END) {
        c.flush_all(pk);
        if (c.wg == odd) c.turn_begin();
        c.leave();
        break;
      }
      if (type == IT_ATTN) {
        attn_consumer(c, pk, item, ii, ibuf, rank, odd);
        continue;
      }
      ii++;
      if (type == IT_PROJ) {
        proj_consumer(c, pk, P, item, rank);
        item = wait_item(ibuf + 4 * ii);
      } else if (out_consumer(c, pk, P, item, ibuf + 4 * ii, rank, __shfl_sync(0xffffffffu, odd, 0))) {
        TRACE_ITEM
        break;
      }
    }
  }
  cluster_wait();
}

typedef CUresult (*EncodeFn)(CUtensorMap*, CUtensorMapDataType, cuuint32_t, void*, const cuuint64_t*, const cuuint64_t*,
                             const cuuint32_t*, const cuuint32_t*, CUtensorMapInterleave, CUtensorMapSwizzle,
                             CUtensorMapL2promotion, CUtensorMapFloatOOBfill);

void make_map(EncodeFn enc, CUtensorMap* tm, const void* ptr, int rows, int cols, int box_rows) {
  cuuint64_t gd[2] = {(cuuint64_t)cols, (cuuint64_t)rows};
  cuuint64_t gs[1] = {(cuuint64_t)cols * 2};
  cuuint32_t bx[2] = {64, (cuuint32_t)box_rows};
  cuuint32_t es[2] = {1, 1};
  enc(tm, CU_TENSOR_MAP_DATA_TYPE_BFLOAT16, 2, const_cast<void*>(ptr), gd, gs, bx, es, CU_TENSOR_MAP_INTERLEAVE_NONE,
      CU_TENSOR_MAP_SWIZZLE_128B, CU_TENSOR_MAP_L2_PROMOTION_L2_256B, CU_TENSOR_MAP_FLOAT_OOB_FILL_NONE);
}

inline uint32_t mk_proj(int asrc, int s, int start, int count) {
  return IT_PROJ | (asrc << 3) | (s << 4) | (start << 8) | ((uint32_t)count << 24);
}
inline uint32_t mk_attn(int h, int J) { return IT_ATTN | (J << 4) | (h << 8); }
inline uint32_t mk_out(int J, int half, int start, int count) { return IT_OUT | (half << 3) | (J << 4) | (start << 8) | ((uint32_t)count << 24); }

void build_schedule(Params& P) {
  int n = 0;
  const int tiles[8] = {5, 6, 7, 8, 8, 9, 10, 11};
  for (int p = 0; p < 64; p++) P.list[n++] = mk_proj(0, p & 7, (p >> 3) * 16, tiles[p >> 3]);
  for (int s = 0; s < 8; s++)
    for (int half = 0; half < 2; half++) P.list[n++] = mk_proj(1, s, 128 + half * 7, 7);
  constexpr int H0 = 24;
  for (int h = 0; h < H0; h++)
    for (int J = 7; J >= 0; J--) P.list[n++] = mk_attn(h, J);
  for (int J = 7; J >= 0; J--)
    for (int h = H0; h < NH; h++) P.list[n++] = mk_attn(h, J);
  const int split[2][5] = {{13, 12, 11, 10, 0}, {11, 10, 9, 8, 8}};
  int first[8][5];
  for (int J = 0; J < 8; J++) {
    const int* sz = split[J == 7];
    const int parts = J == 7 ? 5 : 4;
    int k = 0, early = 0;
    for (int i = 0; i < parts; i++) {
      first[J][i] = k;
      const int late = (NH - H0 - i + parts - 1) / parts;
      for (int j = 0; j < sz[i] - late; j++, early++) P.order[J][k++] = (uint8_t)((early + NH) % NCHUNK);
      for (int j = 0; j < late; j++) P.order[J][k++] = (uint8_t)(H0 + i + j * parts);
    }
  }
  for (int size = 16; size > 0; size--)
    for (int J = 0; J < 8; J++)
      for (int i = 0; i < 5; i++)
        if (split[J == 7][i] == size)
          for (int half = 0; half < 2; half++) P.list[n++] = mk_out(J, half, first[J][i], size);
  P.n_items = n;
}
void finish_schedule(Params& P) {
  for (int J = 0; J < 8; J++)
    for (int i = 0; i < NCHUNK; i++) P.pos[J][P.order[J][i]] = (uint8_t)i;
  int ct = 0;
  for (int t = 0; t < 16; t++)
    for (int i = 0; i < 8; i++)
      if (t < (int)(P.list[8 * i] >> 24)) P.tile[16 * i + t] = (uint8_t)ct++;
  for (int i = 0; i < 32; i++) P.tile[128 + i] = (uint8_t)i;
  for (int p = 0; p < 64; p++) P.list[p] = (P.list[p] & 0xff00ffffu) | P.tile[(P.list[p] >> 8) & 255] << 16;
}

Params g_params;
bool g_ready = false;

}

extern "C" void kernel_launch(void* const* d_in, const int* in_sizes, int n_in, void* d_out, int out_size) {
  (void)in_sizes; (void)n_in; (void)out_size;
  if (!g_ready) {
    EncodeFn enc = nullptr;
    cudaDriverEntryPointQueryResult qr;
    cudaGetDriverEntryPoint("cuTensorMapEncodeTiled", (void**)&enc, cudaEnableDefault, &qr);
    Params& P = g_params;
    memset(&P, 0, sizeof(P));
    make_map(enc, &P.tm_ckv, d_in[1], SEQ, DM, 64);
    make_map(enc, &P.tm_wq, d_in[2], DM, 4096, 128);
    make_map(enc, &P.tm_wuk, d_in[3], DM, 4096, 128);
    make_map(enc, &P.tm_wuv, d_in[4], DM, 4096, 128);
    make_map(enc, &P.tm_wo, d_in[5], 4096, DM, 128);
    make_map(enc, &P.tm_w1, d_in[7], DM, DFF, 128);
    make_map(enc, &P.tm_w2, d_in[8], DFF, DM, 128);
    make_map(enc, &P.tm_out, d_out, SEQ, DM, 16);
    P.x = (const __nv_bfloat16*)d_in[0];
    P.out = (__nv_bfloat16*)d_out;
    build_schedule(P);
    finish_schedule(P);
    cudaFuncSetAttribute(fused_kernel, cudaFuncAttributeMaxDynamicSharedMemorySize, SMEM_BYTES);
    g_ready = true;
  }
  fused_kernel<<<NCTA, 384, SMEM_BYTES>>>(g_params);
}
```
